```python
import torch

def _softmax(x, axis=-1):
    return torch.softmax(x, dim=axis)
def _gelu(x):
    return torch.nn.functional.gelu(x, approximate="tanh")
def _silu(x):
    return torch.nn.functional.silu(x)
def _sigmoid(x):
    return torch.sigmoid(x)
def _layernorm(x, axis=-1, eps=1e-5):
    m = x.mean(dim=axis, keepdim=True)
    v = x.var(dim=axis, keepdim=True, unbiased=False)
    return (x - m) / torch.sqrt(v + eps)
def _scatter_add(tgt, idx, src, axis=0):
    return tgt.clone().index_add_(axis, idx, src)
def _segment_sum(src, seg, n):
    out = torch.zeros((n,) + src.shape[1:], dtype=src.dtype)
    return out.index_add_(0, seg, src)
def _pad(x, pw):
    flat = tuple(v for pair in reversed(pw) for v in pair)
    return torch.nn.functional.pad(x, flat)

kernel_name = 'standalone__mha_block_cached__decode'

def setup_inputs():

    _w = (lambda a: (lambda t: t.to(torch.bfloat16) if t.is_floating_point() else t)(torch.as_tensor(a)))
    B, Sq, D = 4, 1, 448
    H, Sk, Dh = 16, 8192, 256
    return {
        "x": _w((lambda *s: torch.randn(*s, dtype=torch.bfloat16) * 0.8)(B, Sq, D)),
        "k_cache": _w((lambda *s: torch.randn(*s, dtype=torch.bfloat16) * 0.8)(B, H, Sk, Dh)),
        "v_cache": _w((lambda *s: torch.randn(*s, dtype=torch.bfloat16) * 0.05)(B, H, Sk, Dh)),
        "wq": _w((lambda *s: torch.randn(*s, dtype=torch.bfloat16) * 0.8)(D, H * Dh) * (D ** -0.5)),
        "wo": _w((lambda *s: torch.randn(*s, dtype=torch.bfloat16) * 0.05)(H * Dh, D) * ((H * Dh) ** -0.5)),
    }

def reference(x, k_cache, v_cache, wq, wo):
    B, Sq, D = x.shape
    H, Dh = 16, 256
    q = (lambda x, *d: x.permute(*d))((x @ wq).reshape(B, Sq, H, Dh), 0, 2, 1, 3)
    scores = torch.einsum("bhqd,bhkd->bhqk", q, k_cache) * (Dh ** -0.5)
    p = _softmax(scores, axis=-1)
    o = torch.einsum("bhqk,bhkd->bhqd", p, v_cache)
    return (lambda x, *d: x.permute(*d))(o, 0, 2, 1, 3).reshape(B, Sq, H * Dh) @ wo
```

```cpp
#include <cuda_runtime.h>
#include <cuda_bf16.h>
#include <stdint.h>

namespace {

constexpr int NB = 4, DM = 448, NH = 16, SK = 8192, DH = 256;
constexpr int KT = 32;
constexpr int STAGES = 6;
constexpr int KEYS = SK / 2;
constexpr int NT = KEYS / KT;
constexpr int TILE = KT * DH * 2;
constexpr int NCW = 8;
constexpr int NTHREADS = (NCW + 1) * 32;
constexpr int KPW = KT / NCW;
constexpr int HC = DM / 2;

struct __align__(128) Smem {
    unsigned char stage[STAGES][2][TILE];
    float part_o[2 * NCW][DH];
    float part_ml[2 * NCW][2];
    float q[DH];
    float red[NCW][HC];
    float o[DH];
    uint64_t full[STAGES];
    uint64_t empty[STAGES];
    int last;
};

__device__ float g_part[NB][NH][DM];
__device__ unsigned int g_cnt[NB][2];

__device__ __forceinline__ uint32_t smem_u32(const void* p) { return (uint32_t)__cvta_generic_to_shared(p); }
__device__ __forceinline__ void mbar_init(uint32_t a, uint32_t c) {
    asm volatile("mbarrier.init.shared::cta.b64 [%0], %1;" ::"r"(a), "r"(c) : "memory");
}
__device__ __forceinline__ void mbar_expect_tx(uint32_t a, uint32_t b) {
    asm volatile("mbarrier.arrive.expect_tx.shared::cta.b64 _, [%0], %1;" ::"r"(a), "r"(b) : "memory");
}
__device__ __forceinline__ void mbar_arrive(uint32_t a) {
    asm volatile("mbarrier.arrive.shared::cta.b64 _, [%0];" ::"r"(a) : "memory");
}
__device__ __forceinline__ bool mbar_try(uint32_t a, uint32_t ph) {
    uint32_t ok;
    asm volatile(
        "{\n"
        ".reg .pred p;\n"
        "mbarrier.try_wait.parity.shared::cta.b64 p, [%1], %2;\n"
        "selp.u32 %0, 1, 0, p;\n"
        "}\n" : "=r"(ok) : "r"(a), "r"(ph) : "memory");
    return ok != 0;
}
__device__ __forceinline__ void mbar_wait(uint32_t a, uint32_t ph) {
    uint32_t n = 0;
    while (!mbar_try(a, ph)) {
        if (++n > (1u << 24)) __trap();
    }
}
__device__ __forceinline__ void bulk_load(uint32_t dst, const void* src, uint32_t bytes, uint32_t mbar) {
    asm volatile("cp.async.bulk.shared::cluster.global.mbarrier::complete_tx::bytes [%0], [%1], %2, [%3];"
                 ::"r"(dst), "l"(src), "r"(bytes), "r"(mbar) : "memory");
}
__device__ __forceinline__ void cluster_arrive() { asm volatile("barrier.cluster.arrive.release.aligned;" ::: "memory"); }
__device__ __forceinline__ void cluster_arrive_relaxed() { asm volatile("barrier.cluster.arrive.relaxed.aligned;" ::: "memory"); }
__device__ __forceinline__ void cluster_wait() { asm volatile("barrier.cluster.wait.acquire.aligned;" ::: "memory"); }
__device__ __forceinline__ uint32_t mapa(uint32_t a, uint32_t rank) {
    uint32_t r;
    asm volatile("mapa.shared::cluster.u32 %0, %1, %2;" : "=r"(r) : "r"(a), "r"(rank));
    return r;
}
__device__ __forceinline__ void st_cluster_f32(uint32_t a, float v) {
    asm volatile("st.shared::cluster.f32 [%0], %1;" ::"r"(a), "f"(v) : "memory");
}
__device__ __forceinline__ void st_cluster_v4(uint32_t a, float x, float y, float z, float w) {
    asm volatile("st.shared::cluster.v4.f32 [%0], {%1,%2,%3,%4};" ::"r"(a), "f"(x), "f"(y), "f"(z), "f"(w) : "memory");
}
__device__ __forceinline__ void consumer_sync() { asm volatile("bar.sync 1, 256;" ::: "memory"); }
__device__ __forceinline__ uint4 ldg_nc(const void* p) {
    uint4 v;
    asm volatile("ld.global.nc.L1::no_allocate.v4.u32 {%0,%1,%2,%3}, [%4];"
                 : "=r"(v.x), "=r"(v.y), "=r"(v.z), "=r"(v.w) : "l"(p));
    return v;
}
__device__ __forceinline__ uint4 lds128(uint32_t a) {
    uint4 v;
    asm volatile("ld.shared.v4.u32 {%0,%1,%2,%3}, [%4];" : "=r"(v.x), "=r"(v.y), "=r"(v.z), "=r"(v.w) : "r"(a));
    return v;
}
__device__ __forceinline__ float bf_lo(uint32_t u) { return __uint_as_float(u << 16); }
__device__ __forceinline__ float bf_hi(uint32_t u) { return __uint_as_float(u & 0xffff0000u); }
__device__ __forceinline__ float ex2(float x) {
    float y;
    asm("ex2.approx.ftz.f32 %0, %1;" : "=f"(y) : "f"(x));
    return y;
}
__device__ __forceinline__ float round_bf16(float x) { return __bfloat162float(__float2bfloat16_rn(x)); }

__device__ __forceinline__ float dot8(const uint4& a, const float* q) {
    float s = bf_lo(a.x) * q[0];
    s = fmaf(bf_hi(a.x), q[1], s);
    s = fmaf(bf_lo(a.y), q[2], s);
    s = fmaf(bf_hi(a.y), q[3], s);
    s = fmaf(bf_lo(a.z), q[4], s);
    s = fmaf(bf_hi(a.z), q[5], s);
    s = fmaf(bf_lo(a.w), q[6], s);
    s = fmaf(bf_hi(a.w), q[7], s);
    return s;
}
__device__ __forceinline__ void axpy8(float* o, float p, const uint4& a) {
    o[0] = fmaf(p, bf_lo(a.x), o[0]);
    o[1] = fmaf(p, bf_hi(a.x), o[1]);
    o[2] = fmaf(p, bf_lo(a.y), o[2]);
    o[3] = fmaf(p, bf_hi(a.y), o[3]);
    o[4] = fmaf(p, bf_lo(a.z), o[4]);
    o[5] = fmaf(p, bf_hi(a.z), o[5]);
    o[6] = fmaf(p, bf_lo(a.w), o[6]);
    o[7] = fmaf(p, bf_hi(a.w), o[7]);
}

__global__ void __cluster_dims__(2, 1, 1) __launch_bounds__(NTHREADS, 1)
mha_decode_kernel(const __nv_bfloat16* __restrict__ x, const __nv_bfloat16* __restrict__ kc,
                  const __nv_bfloat16* __restrict__ vc, const __nv_bfloat16* __restrict__ wq,
                  const __nv_bfloat16* __restrict__ wo, __nv_bfloat16* __restrict__ out) {
    extern __shared__ __align__(128) unsigned char smem_raw[];
    Smem& sm = *reinterpret_cast<Smem*>(smem_raw);

    const int tid = threadIdx.x;
    const int warp = tid >> 5, lane = tid & 31;
    const int rank = blockIdx.x & 1;
    const int pair = blockIdx.x >> 1;
    const int b = pair >> 4, h = pair & 15;

    if (tid == NCW * 32) {
#pragma unroll
        for (int s = 0; s < STAGES; s++) {
            mbar_init(smem_u32(&sm.full[s]), 1);
            mbar_init(smem_u32(&sm.empty[s]), NCW);
        }
        asm volatile("fence.mbarrier_init.release.cluster;" ::: "memory");
        asm volatile("fence.proxy.async.shared::cta;" ::: "memory");
    }

    if (warp == NCW) {
        const unsigned char* kbase = reinterpret_cast<const unsigned char*>(kc) +
                                     ((size_t)pair * SK + (size_t)rank * KEYS) * (DH * 2);
        const unsigned char* vbase = reinterpret_cast<const unsigned char*>(vc) +
                                     ((size_t)pair * SK + (size_t)rank * KEYS) * (DH * 2);
        if (lane == 0) {
#pragma unroll
            for (int s = 0; s < STAGES; s++) {
                const uint32_t fb = smem_u32(&sm.full[s]);
                mbar_expect_tx(fb, 2 * TILE);
                bulk_load(smem_u32(sm.stage[s][0]), kbase + (size_t)s * TILE, TILE, fb);
                bulk_load(smem_u32(sm.stage[s][1]), vbase + (size_t)s * TILE, TILE, fb);
            }
        }
        __syncwarp();
        __syncthreads();
        cluster_arrive_relaxed();
        cluster_wait();
        cluster_arrive_relaxed();
        if (lane == 0) {
            int s = 0, ph = 0;
            for (int it = STAGES; it < NT; it++) {
                mbar_wait(smem_u32(&sm.empty[s]), ph);
                const uint32_t fb = smem_u32(&sm.full[s]);
                mbar_expect_tx(fb, 2 * TILE);
                bulk_load(smem_u32(sm.stage[s][0]), kbase + (size_t)it * TILE, TILE, fb);
                bulk_load(smem_u32(sm.stage[s][1]), vbase + (size_t)it * TILE, TILE, fb);
                if (++s == STAGES) { s = 0; ph ^= 1; }
            }
        }
        return;
    }

    {
        const int cq = tid & 15, rg = tid >> 4;
        const __nv_bfloat16* wp = wq + (size_t)(rg * 28) * (NH * DH) + h * DH + rank * 128 + cq * 8;
        uint4 w[28];
#pragma unroll
        for (int i = 0; i < 28; i++) w[i] = ldg_nc(wp + (size_t)i * (NH * DH));
        uint2 xv[7];
        const uint2* xp = reinterpret_cast<const uint2*>(x + b * DM + rg * 28);
#pragma unroll
        for (int i = 0; i < 7; i++) xv[i] = __ldg(xp + i);
        __syncthreads();
        cluster_arrive_relaxed();
        float acc[8];
#pragma unroll
        for (int j = 0; j < 8; j++) acc[j] = 0.f;
#pragma unroll
        for (int i = 0; i < 7; i++) {
            axpy8(acc, bf_lo(xv[i].x), w[4 * i + 0]);
            axpy8(acc, bf_hi(xv[i].x), w[4 * i + 1]);
            axpy8(acc, bf_lo(xv[i].y), w[4 * i + 2]);
            axpy8(acc, bf_hi(xv[i].y), w[4 * i + 3]);
        }
#pragma unroll
        for (int j = 0; j < 8; j++) acc[j] += __shfl_xor_sync(0xffffffffu, acc[j], 16);
        if (lane < 16) {
            *reinterpret_cast<float4*>(&sm.red[warp][cq * 8]) = make_float4(acc[0], acc[1], acc[2], acc[3]);
            *reinterpret_cast<float4*>(&sm.red[warp][cq * 8 + 4]) = make_float4(acc[4], acc[5], acc[6], acc[7]);
        }
        consumer_sync();
        cluster_wait();
        if (tid < 128) {
            float s = 0.f;
#pragma unroll
            for (int g = 0; g < NCW; g++) s += sm.red[g][tid];
            s = round_bf16(s) * (1.4426950408889634f * 0.0625f);
            const uint32_t a = smem_u32(&sm.q[rank * 128 + tid]);
            sm.q[rank * 128 + tid] = s;
            st_cluster_f32(mapa(a, rank ^ 1), s);
        }
        cluster_arrive();
    }

    uint4 wreg[32];
    {
        const __nv_bfloat16* wp = wo + (size_t)(h * DH + warp * 32) * DM + rank * HC + (lane < 28 ? lane : 0) * 8;
#pragma unroll
        for (int i = 0; i < 32; i++) wreg[i] = ldg_nc(wp + (size_t)i * DM);
    }

    cluster_wait();
    float q[8];
    {
        const float4 a = *reinterpret_cast<const float4*>(&sm.q[lane * 8]);
        const float4 c = *reinterpret_cast<const float4*>(&sm.q[lane * 8 + 4]);
        q[0] = a.x; q[1] = a.y; q[2] = a.z; q[3] = a.w;
        q[4] = c.x; q[5] = c.y; q[6] = c.z; q[7] = c.w;
    }

    float o[8];
#pragma unroll
    for (int j = 0; j < 8; j++) o[j] = 0.f;
    float m = -INFINITY, l = 0.f;
    const bool hi16 = lane & 16, hi8 = lane & 8;
    const uint32_t tile_off = (uint32_t)(warp * KPW * DH * 2 + lane * 16);

    int s = 0, ph = 0;
    for (int it = 0; it < NT; it++) {
        mbar_wait(smem_u32(&sm.full[s]), ph);
        const uint32_t ka = smem_u32(sm.stage[s][0]) + tile_off;
        uint4 kk[KPW], vv[KPW];
#pragma unroll
        for (int j = 0; j < KPW; j++) kk[j] = lds128(ka + j * (DH * 2));
#pragma unroll
        for (int j = 0; j < KPW; j++) vv[j] = lds128(ka + TILE + j * (DH * 2));
        float sc[KPW];
#pragma unroll
        for (int j = 0; j < KPW; j++) sc[j] = dot8(kk[j], q);
        float k0 = hi16 ? sc[2] : sc[0], k1 = hi16 ? sc[3] : sc[1];
        const float s0 = hi16 ? sc[0] : sc[2], s1 = hi16 ? sc[1] : sc[3];
        k0 += __shfl_xor_sync(0xffffffffu, s0, 16);
        k1 += __shfl_xor_sync(0xffffffffu, s1, 16);
        float kv = hi8 ? k1 : k0;
        const float sv = hi8 ? k0 : k1;
        kv += __shfl_xor_sync(0xffffffffu, sv, 8);
        kv += __shfl_xor_sync(0xffffffffu, kv, 4);
        kv += __shfl_xor_sync(0xffffffffu, kv, 2);
        kv += __shfl_xor_sync(0xffffffffu, kv, 1);
        __syncwarp();
        if (lane == 0) mbar_arrive(smem_u32(&sm.empty[s]));
        float mx = fmaxf(kv, __shfl_xor_sync(0xffffffffu, kv, 8));
        mx = fmaxf(mx, __shfl_xor_sync(0xffffffffu, mx, 16));
        const float mn = fmaxf(m, mx);
        const float p = ex2(kv - mn);
        const float alpha = ex2(m - mn);
        m = mn;
        const float p0 = __shfl_sync(0xffffffffu, p, 0);
        const float p1 = __shfl_sync(0xffffffffu, p, 8);
        const float p2 = __shfl_sync(0xffffffffu, p, 16);
        const float p3 = __shfl_sync(0xffffffffu, p, 24);
        l = fmaf(l, alpha, (p0 + p1) + (p2 + p3));
#pragma unroll
        for (int j = 0; j < 8; j++) o[j] *= alpha;
        axpy8(o, p0, vv[0]);
        axpy8(o, p1, vv[1]);
        axpy8(o, p2, vv[2]);
        axpy8(o, p3, vv[3]);
        if (++s == STAGES) { s = 0; ph ^= 1; }
    }

    {
        const int slot = rank * NCW + warp;
        const uint32_t a = smem_u32(&sm.part_o[slot][lane * 8]);
        const uint32_t ra = mapa(a, rank ^ 1);
        *reinterpret_cast<float4*>(&sm.part_o[slot][lane * 8]) = make_float4(o[0], o[1], o[2], o[3]);
        *reinterpret_cast<float4*>(&sm.part_o[slot][lane * 8 + 4]) = make_float4(o[4], o[5], o[6], o[7]);
        st_cluster_v4(ra, o[0], o[1], o[2], o[3]);
        st_cluster_v4(ra + 16, o[4], o[5], o[6], o[7]);
        if (lane == 0) {
            const uint32_t am = smem_u32(&sm.part_ml[slot][0]);
            const uint32_t rm = mapa(am, rank ^ 1);
            sm.part_ml[slot][0] = m;
            sm.part_ml[slot][1] = l;
            st_cluster_f32(rm, m);
            st_cluster_f32(rm + 4, l);
        }
    }
    cluster_arrive();
    cluster_wait();
    {
        float mm = -INFINITY;
#pragma unroll
        for (int g = 0; g < 2 * NCW; g++) mm = fmaxf(mm, sm.part_ml[g][0]);
        float lt = 0.f, ot = 0.f;
#pragma unroll
        for (int g = 0; g < 2 * NCW; g++) {
            const float wgt = ex2(sm.part_ml[g][0] - mm);
            lt = fmaf(wgt, sm.part_ml[g][1], lt);
            ot = fmaf(wgt, sm.part_o[g][tid], ot);
        }
        sm.o[tid] = round_bf16(ot / lt);
    }
    consumer_sync();
    {
        float acc[8];
#pragma unroll
        for (int j = 0; j < 8; j++) acc[j] = 0.f;
#pragma unroll
        for (int i4 = 0; i4 < 8; i4++) {
            const float4 ov = *reinterpret_cast<const float4*>(&sm.o[warp * 32 + i4 * 4]);
            axpy8(acc, ov.x, wreg[i4 * 4 + 0]);
            axpy8(acc, ov.y, wreg[i4 * 4 + 1]);
            axpy8(acc, ov.z, wreg[i4 * 4 + 2]);
            axpy8(acc, ov.w, wreg[i4 * 4 + 3]);
        }
        if (lane < 28) {
            *reinterpret_cast<float4*>(&sm.red[warp][lane * 8]) = make_float4(acc[0], acc[1], acc[2], acc[3]);
            *reinterpret_cast<float4*>(&sm.red[warp][lane * 8 + 4]) = make_float4(acc[4], acc[5], acc[6], acc[7]);
        }
    }
    consumer_sync();
    if (tid < HC) {
        float y = 0.f;
#pragma unroll
        for (int g = 0; g < NCW; g++) y += sm.red[g][tid];
        __stcg(&g_part[b][h][rank * HC + tid], y);
    }
    consumer_sync();
    if (tid == 0) {
        __threadfence();
        const unsigned int old = atomicAdd(&g_cnt[b][rank], 1u);
        sm.last = (old == NH - 1);
    }
    consumer_sync();
    if (sm.last) {
        __threadfence();
        if (tid < HC) {
            float y = 0.f;
#pragma unroll
            for (int hh = 0; hh < NH; hh++) y += __ldcg(&g_part[b][hh][rank * HC + tid]);
            out[b * DM + rank * HC + tid] = __float2bfloat16_rn(y);
        }
        if (tid == 0) g_cnt[b][rank] = 0;
    }
}

}

extern "C" void kernel_launch(void* const* d_in, const int* in_sizes, int n_in,
                              void* d_out, int out_size) {
    const __nv_bfloat16* x = (const __nv_bfloat16*)d_in[0];
    const __nv_bfloat16* kc = (const __nv_bfloat16*)d_in[1];
    const __nv_bfloat16* vc = (const __nv_bfloat16*)d_in[2];
    const __nv_bfloat16* wq = (const __nv_bfloat16*)d_in[3];
    const __nv_bfloat16* wo = (const __nv_bfloat16*)d_in[4];
    __nv_bfloat16* out = (__nv_bfloat16*)d_out;
    cudaFuncSetAttribute(mha_decode_kernel, cudaFuncAttributeMaxDynamicSharedMemorySize, (int)sizeof(Smem));
    mha_decode_kernel<<<NB * NH * 2, NTHREADS, sizeof(Smem)>>>(x, kc, vc, wq, wo, out);
}
```

```cpp
#include <cuda_runtime.h>
#include <cuda_bf16.h>
#include <stdint.h>

namespace {

constexpr int NB = 4, DM = 448, NH = 16, SK = 8192, DH = 256;
constexpr int NPAIR = NB * NH;
constexpr int KT = 32;
constexpr int STAGES = 4;
constexpr int TILE = KT * DH * 2;
constexpr int TPP = SK / KT;
constexpr int NTILES = NPAIR * TPP;
constexpr int NCTA = 132;
constexpr int NSLICE = 128;
constexpr int NCW = 8;
constexpr int W_PROD = 8, W_SIG = 9, W_EPI = 10, NEPI = 4;
constexpr int NTHREADS = (W_EPI + NEPI) * 32;
constexpr int KPW = KT / NCW;
constexpr int SIGQ = 4;
constexpr int RPW = NCTA / NEPI;
constexpr int HEAD_STAGES = 1;
constexpr int HALF_TILES = NCTA * 4;
constexpr int TAPER_TILES = NCTA * 8;
constexpr float SCALE_LOG2E = 1.4426950408889634f * 0.0625f;

struct __align__(128) Smem {
    unsigned char stage[STAGES][2][TILE];
    __nv_bfloat16 qall[NPAIR][DH];
    __nv_bfloat16 wo_s[32][DM];
    float fo[2][NCW][DH];
    float fml[2][NCW][2];
    float xs[NB][DM];
    float qred[NCW][128];
    float ew[NEPI][160];
    float eo[2][NEPI][32];
    uint64_t full[STAGES];
    uint64_t empty[STAGES];
    uint64_t sig_full[SIGQ];
    uint64_t sig_empty[SIGQ];
    uint64_t wo_bar;
    uint64_t wq_bar;
    int qready[NPAIR];
    int tile_pair[STAGES];
    int sig_pair[SIGQ];
    int sig_nt[SIGQ];
    unsigned int epoch;
    int elast;
};
static_assert(sizeof(Smem) <= 227 * 1024, "shared memory budget");

struct __align__(128) State {
    unsigned int tile_ctr;  unsigned int pad0[31];
    unsigned int exit_cnt;  unsigned int pad1[31];
    unsigned int done[NB];  unsigned int pad2[28];
    unsigned int cnt[NPAIR];
    float acc[NB][DM];
};

__device__ State g_state[2];
__device__ unsigned int g_epoch;
__device__ __align__(16) uint2 g_qll[NPAIR * DH / 2];
__device__ __align__(16) float g_rec[NPAIR][NCTA][DH];
__device__ float4 g_hdr[NPAIR][NCTA];

__device__ __forceinline__ uint32_t smem_u32(const void* p) { return (uint32_t)__cvta_generic_to_shared(p); }
__device__ __forceinline__ void mbar_init(uint32_t a, uint32_t c) {
    asm volatile("mbarrier.init.shared::cta.b64 [%0], %1;" ::"r"(a), "r"(c) : "memory");
}
__device__ __forceinline__ void mbar_expect_tx(uint32_t a, uint32_t b) {
    asm volatile("mbarrier.arrive.expect_tx.shared::cta.b64 _, [%0], %1;" ::"r"(a), "r"(b) : "memory");
}
__device__ __forceinline__ void mbar_arrive(uint32_t a) {
    asm volatile("mbarrier.arrive.shared::cta.b64 _, [%0];" ::"r"(a) : "memory");
}
__device__ __forceinline__ bool mbar_try(uint32_t a, uint32_t ph) {
    uint32_t ok;
    asm volatile(
        "{\n"
        ".reg .pred p;\n"
        "mbarrier.try_wait.parity.shared::cta.b64 p, [%1], %2;\n"
        "selp.u32 %0, 1, 0, p;\n"
        "}\n" : "=r"(ok) : "r"(a), "r"(ph) : "memory");
    return ok != 0;
}
__device__ __forceinline__ void mbar_wait(uint32_t a, uint32_t ph) {
    uint32_t n = 0;
    while (!mbar_try(a, ph)) {
        if (++n > (1u << 24)) __trap();
    }
}
__device__ __forceinline__ void bulk_load(uint32_t dst, const void* src, uint32_t bytes, uint32_t mbar) {
    asm volatile("cp.async.bulk.shared::cluster.global.mbarrier::complete_tx::bytes [%0], [%1], %2, [%3];"
                 ::"r"(dst), "l"(src), "r"(bytes), "r"(mbar) : "memory");
}
__device__ __forceinline__ void bulk_load_hint(uint32_t dst, const void* src, uint32_t bytes, uint32_t mbar, uint64_t pol) {
    asm volatile("cp.async.bulk.shared::cluster.global.mbarrier::complete_tx::bytes.L2::cache_hint [%0], [%1], %2, [%3], %4;"
                 ::"r"(dst), "l"(src), "r"(bytes), "r"(mbar), "l"(pol) : "memory");
}
__device__ __forceinline__ uint64_t policy_evict_first() {
    uint64_t pol;
    asm volatile("createpolicy.fractional.L2::evict_first.b64 %0, 1.0;" : "=l"(pol));
    return pol;
}
__device__ __forceinline__ void bar_sync(int id, int n) { asm volatile("bar.sync %0, %1;" ::"r"(id), "r"(n) : "memory"); }
__device__ __forceinline__ unsigned int ld_acquire(const unsigned int* p) {
    unsigned int v;
    asm volatile("ld.acquire.gpu.global.u32 %0, [%1];" : "=r"(v) : "l"(p) : "memory");
    return v;
}
__device__ __forceinline__ void poll_ge(const unsigned int* p, unsigned int target) {
    uint32_t n = 0, v;
    while ((v = ld_acquire(p)) < target) {
        __nanosleep(v == 0 ? 1000 : 40);
        if (++n > (1u << 22)) __trap();
    }
}
__device__ __forceinline__ void red_release_add_u32(unsigned int* p, unsigned int v) {
    asm volatile("red.release.gpu.global.add.u32 [%0], %1;" ::"l"(p), "r"(v) : "memory");
}
__device__ __forceinline__ unsigned int atom_acqrel_add_u32(unsigned int* p, unsigned int v) {
    unsigned int r;
    asm volatile("atom.acq_rel.gpu.global.add.u32 %0, [%1], %2;" : "=r"(r) : "l"(p), "r"(v) : "memory");
    return r;
}
__device__ __forceinline__ void red_add_v4(float* p, float a, float b, float c, float d) {
    asm volatile("red.relaxed.gpu.global.v4.f32.add [%0], {%1,%2,%3,%4};" ::"l"(p), "f"(a), "f"(b), "f"(c), "f"(d) : "memory");
}
__device__ __forceinline__ float ld_gpu_f32(const float* p) {
    float v;
    asm volatile("ld.relaxed.gpu.global.f32 %0, [%1];" : "=f"(v) : "l"(p) : "memory");
    return v;
}
__device__ __forceinline__ float4 ld_gpu_v4(const float4* p) {
    float4 v;
    asm volatile("ld.relaxed.gpu.global.v4.f32 {%0,%1,%2,%3}, [%4];" : "=f"(v.x), "=f"(v.y), "=f"(v.z), "=f"(v.w) : "l"(p) : "memory");
    return v;
}
__device__ __forceinline__ void st_release_cta(int* p, int v) {
    asm volatile("st.release.cta.shared.s32 [%0], %1;" ::"r"(smem_u32(p)), "r"(v) : "memory");
}
__device__ __forceinline__ int ld_acquire_cta(const int* p) {
    int v;
    asm volatile("ld.acquire.cta.shared.s32 %0, [%1];" : "=r"(v) : "r"(smem_u32(p)) : "memory");
    return v;
}
__device__ __forceinline__ void st_ll(uint2* p, uint32_t payload, uint32_t tag) {
    const unsigned long long v = ((unsigned long long)tag << 32) | payload;
    asm volatile("st.relaxed.gpu.global.u64 [%0], %1;" ::"l"(p), "l"(v) : "memory");
}
__device__ __forceinline__ uint4 ld_ll2(const uint2* p) {
    unsigned long long a, b;
    asm volatile("ld.relaxed.gpu.global.v2.u64 {%0,%1}, [%2];" : "=l"(a), "=l"(b) : "l"(p) : "memory");
    return make_uint4((uint32_t)a, (uint32_t)(a >> 32), (uint32_t)b, (uint32_t)(b >> 32));
}
__device__ __forceinline__ uint4 ldg_nc(const void* p) {
    uint4 v;
    asm volatile("ld.global.nc.L1::no_allocate.v4.u32 {%0,%1,%2,%3}, [%4];"
                 : "=r"(v.x), "=r"(v.y), "=r"(v.z), "=r"(v.w) : "l"(p));
    return v;
}
__device__ __forceinline__ uint4 lds128(uint32_t a) {
    uint4 v;
    asm volatile("ld.shared.v4.u32 {%0,%1,%2,%3}, [%4];" : "=r"(v.x), "=r"(v.y), "=r"(v.z), "=r"(v.w) : "r"(a));
    return v;
}
__device__ __forceinline__ float bf_lo(uint32_t u) { return __uint_as_float(u << 16); }
__device__ __forceinline__ float bf_hi(uint32_t u) { return __uint_as_float(u & 0xffff0000u); }
__device__ __forceinline__ float ex2(float x) {
    float y;
    asm("ex2.approx.ftz.f32 %0, %1;" : "=f"(y) : "f"(x));
    return y;
}
__device__ __forceinline__ float round_bf16(float x) { return __bfloat162float(__float2bfloat16_rn(x)); }

__device__ __forceinline__ float dot8(const uint4& a, const float* q) {
    float s = bf_lo(a.x) * q[0];
    s = fmaf(bf_hi(a.x), q[1], s);
    s = fmaf(bf_lo(a.y), q[2], s);
    s = fmaf(bf_hi(a.y), q[3], s);
    s = fmaf(bf_lo(a.z), q[4], s);
    s = fmaf(bf_hi(a.z), q[5], s);
    s = fmaf(bf_lo(a.w), q[6], s);
    s = fmaf(bf_hi(a.w), q[7], s);
    return s;
}
__device__ __forceinline__ void axpy8(float* o, float p, const uint4& a) {
    o[0] = fmaf(p, bf_lo(a.x), o[0]);
    o[1] = fmaf(p, bf_hi(a.x), o[1]);
    o[2] = fmaf(p, bf_lo(a.y), o[2]);
    o[3] = fmaf(p, bf_hi(a.y), o[3]);
    o[4] = fmaf(p, bf_lo(a.z), o[4]);
    o[5] = fmaf(p, bf_hi(a.z), o[5]);
    o[6] = fmaf(p, bf_lo(a.w), o[6]);
    o[7] = fmaf(p, bf_hi(a.w), o[7]);
}

__global__ void __launch_bounds__(NTHREADS, 1)
mha_decode_kernel(const __nv_bfloat16* __restrict__ x, const __nv_bfloat16* __restrict__ kc,
                  const __nv_bfloat16* __restrict__ vc, const __nv_bfloat16* __restrict__ wq,
                  const __nv_bfloat16* __restrict__ wo, __nv_bfloat16* __restrict__ out) {
    extern __shared__ __align__(128) unsigned char smem_raw[];
    Smem& sm = *reinterpret_cast<Smem*>(smem_raw);

    const int tid = threadIdx.x;
    const int warp = tid >> 5, lane = tid & 31;
    const int cta = blockIdx.x;
    const unsigned char* kbase = reinterpret_cast<const unsigned char*>(kc);
    const unsigned char* vbase = reinterpret_cast<const unsigned char*>(vc);

    uint4 w[7];
    if (warp < NCW) {
        if (cta < NSLICE) {
            const __nv_bfloat16* wp = wq + (size_t)((tid >> 2) * 7) * (NH * DH) + cta * 32 + (tid & 3) * 8;
#pragma unroll
            for (int i = 0; i < 7; i++) w[i] = ldg_nc(wp + (size_t)i * (NH * DH));
        }
#pragma unroll
        for (int i = 0; i < 7; i++) (&sm.xs[0][0])[tid + 256 * i] = __bfloat162float(x[tid + 256 * i]);
    } else if (warp >= W_EPI) {
        if (tid - W_EPI * 32 < NPAIR) sm.qready[tid - W_EPI * 32] = 0;
    } else if (tid == W_PROD * 32) {
#pragma unroll
        for (int s = 0; s < STAGES; s++) {
            mbar_init(smem_u32(&sm.full[s]), 1);
            mbar_init(smem_u32(&sm.empty[s]), NCW);
        }
#pragma unroll
        for (int s = 0; s < SIGQ; s++) {
            mbar_init(smem_u32(&sm.sig_full[s]), NCW);
            mbar_init(smem_u32(&sm.sig_empty[s]), 1);
        }
        mbar_init(smem_u32(&sm.wo_bar), 1);
        mbar_init(smem_u32(&sm.wq_bar), cta < NSLICE ? NCW : 1);
        asm volatile("fence.mbarrier_init.release.cluster;" ::: "memory");
        asm volatile("fence.proxy.async.shared::cta;" ::: "memory");
        const uint64_t pol = policy_evict_first();
#pragma unroll
        for (int n = 0; n < HEAD_STAGES; n++) {
            const unsigned int t = cta + n * NCTA;
            const uint32_t fb = smem_u32(&sm.full[n]);
            sm.tile_pair[n] = (int)(t / TPP);
            mbar_expect_tx(fb, 2 * TILE);
            bulk_load_hint(smem_u32(sm.stage[n][0]), kbase + (size_t)t * TILE, TILE, fb, pol);
            bulk_load_hint(smem_u32(sm.stage[n][1]), vbase + (size_t)t * TILE, TILE, fb, pol);
        }
        sm.epoch = g_epoch;
    }
    __syncthreads();
    const unsigned int epoch = sm.epoch;
    State* st = &g_state[epoch & 1];
    const unsigned int tag = epoch + 1;

    if (warp == W_PROD) {
        if (lane == 0) {
            const uint64_t pol = policy_evict_first();
            constexpr unsigned int NFULL = NTILES - HALF_TILES;
            constexpr unsigned int NITEMS = NFULL + 2 * HALF_TILES;
            unsigned int tn = atomicAdd(&st->tile_ctr, 1u) + HEAD_STAGES * NCTA;
            mbar_wait(smem_u32(&sm.wq_bar), 0);
            for (int n = HEAD_STAGES;; n++) {
                const int s = n % STAGES;
                const unsigned int t = tn;
                const bool taper = t >= (unsigned)(NTILES - TAPER_TILES);
                if (!taper) tn = atomicAdd(&st->tile_ctr, 1u) + HEAD_STAGES * NCTA;
                if (n >= STAGES) mbar_wait(smem_u32(&sm.empty[s]), ((n / STAGES) & 1) ^ 1);
                const uint32_t fb = smem_u32(&sm.full[s]);
                if (t >= NITEMS) {
                    sm.tile_pair[s] = -1;
                    mbar_arrive(fb);
                    break;
                }
                const bool half = t >= NFULL;
                const size_t off = half ? (size_t)NFULL * TILE + (size_t)(t - NFULL) * (TILE / 2) : (size_t)t * TILE;
                const uint32_t bytes = half ? TILE / 2 : TILE;
                sm.tile_pair[s] = (int)(off / ((size_t)TPP * TILE)) | (half ? 0x10000 : 0);
                mbar_expect_tx(fb, 2 * bytes);
                bulk_load_hint(smem_u32(sm.stage[s][0]), kbase + off, bytes, fb, pol);
                bulk_load_hint(smem_u32(sm.stage[s][1]), vbase + off, bytes, fb, pol);
                if (taper) {
                    const int m = n + 1 - STAGES;
                    if (m >= 0) mbar_wait(smem_u32(&sm.empty[m % STAGES]), (m / STAGES) & 1);
                    tn = atomicAdd(&st->tile_ctr, 1u) + HEAD_STAGES * NCTA;
                }
            }
        }
        return;
    }

    if (warp == W_SIG) {
        if (lane == 0) {
            if (atomicAdd(&st->exit_cnt, 1u) == NCTA - 1) g_epoch = epoch + 1;
            for (int k = 0;; k++) {
                const int slot = k % SIGQ;
                mbar_wait(smem_u32(&sm.sig_full[slot]), (k / SIGQ) & 1);
                const int P = sm.sig_pair[slot], nt = sm.sig_nt[slot];
                if (P < 0) break;
                red_release_add_u32(&st->cnt[P], (unsigned int)nt);
                mbar_arrive(smem_u32(&sm.sig_empty[slot]));
            }
        }
        return;
    }

    if (warp >= W_EPI) {
        const int et = tid - W_EPI * 32, ewp = warp - W_EPI;
        for (int P = ewp; P < NPAIR; P += NEPI) {
            const uint2* src = &g_qll[P * (DH / 2) + lane * 4];
            uint4 t0 = ld_ll2(src), t1 = ld_ll2(src + 2);
            uint32_t n = 0;
            while (t0.y != tag || t0.w != tag || t1.y != tag || t1.w != tag) {
                if (++n > (1u << 22)) __trap();
                t0 = ld_ll2(src); t1 = ld_ll2(src + 2);
            }
            *reinterpret_cast<uint4*>(&sm.qall[P][lane * 8]) = make_uint4(t0.x, t0.z, t1.x, t1.z);
            __syncwarp();
            if (lane == 0) st_release_cta(&sm.qready[P], 1);
        }
        if (cta < NSLICE) {
            const int h = cta >> 3, sl = cta & 7;
            const int col = (et < DM / 4 ? et : 0) * 4;
            for (int b = 0; b < NB; b++) {
                const int P = b * NH + h;
                if (et == 0) {
                    poll_ge(&st->cnt[P], 2 * TPP);
                    if (b == 0) {
                        mbar_expect_tx(smem_u32(&sm.wo_bar), 32 * DM * 2);
                        bulk_load(smem_u32(&sm.wo_s[0][0]), wo + (size_t)cta * 32 * DM, 32 * DM * 2, smem_u32(&sm.wo_bar));
                    }
                }
                bar_sync(3, NEPI * 32);
                float4 hd[5];
#pragma unroll
                for (int i = 0; i < 5; i++) hd[i] = ld_gpu_v4(&g_hdr[P][i < 4 || lane < NCTA - 128 ? lane + 32 * i : 0]);
                float rv[RPW];
#pragma unroll
                for (int i = 0; i < RPW; i++) rv[i] = ld_gpu_f32(&g_rec[P][ewp * RPW + i][sl * 32 + lane]);
                float hm[5], hl[5];
#pragma unroll
                for (int i = 0; i < 5; i++) {
                    const bool ok = (i < 4 || lane < NCTA - 128) && __float_as_uint(hd[i].z) == tag;
                    hm[i] = ok ? hd[i].x : -INFINITY;
                    hl[i] = ok ? hd[i].y : 0.f;
                }
                float M = fmaxf(fmaxf(fmaxf(hm[0], hm[1]), fmaxf(hm[2], hm[3])), hm[4]);
#pragma unroll
                for (int o = 16; o; o >>= 1) M = fmaxf(M, __shfl_xor_sync(0xffffffffu, M, o));
                float L = 0.f;
#pragma unroll
                for (int i = 0; i < 5; i++) {
                    const float wg = ex2(hm[i] - M);
                    L = fmaf(wg, hl[i], L);
                    sm.ew[ewp][lane + 32 * i] = wg;
                }
#pragma unroll
                for (int o = 16; o; o >>= 1) L += __shfl_xor_sync(0xffffffffu, L, o);
                __syncwarp();
                float O[3] = {0.f, 0.f, 0.f};
#pragma unroll
                for (int i = 0; i < RPW; i++) {
                    const float wg = sm.ew[ewp][ewp * RPW + i];
                    O[i % 3] = fmaf(wg, wg != 0.f ? rv[i] : 0.f, O[i % 3]);
                }
                sm.eo[b & 1][ewp][lane] = (O[0] + O[1]) + O[2];
                bar_sync(3, NEPI * 32);
                if (b == 0) mbar_wait(smem_u32(&sm.wo_bar), 0);
                const float ov = round_bf16(((sm.eo[b & 1][0][lane] + sm.eo[b & 1][1][lane]) +
                                             (sm.eo[b & 1][2][lane] + sm.eo[b & 1][3][lane])) / L);
                float y0 = 0.f, y1 = 0.f, y2 = 0.f, y3 = 0.f;
#pragma unroll
                for (int d = 0; d < 32; d++) {
                    const float od = __shfl_sync(0xffffffffu, ov, d);
                    const uint2 wv = *reinterpret_cast<const uint2*>(&sm.wo_s[d][col]);
                    y0 = fmaf(od, bf_lo(wv.x), y0);
                    y1 = fmaf(od, bf_hi(wv.x), y1);
                    y2 = fmaf(od, bf_lo(wv.y), y2);
                    y3 = fmaf(od, bf_hi(wv.y), y3);
                }
                if (et < DM / 4) red_add_v4(&st->acc[b][col], y0, y1, y2, y3);
                bar_sync(3, NEPI * 32);
                if (et == 0) sm.elast = (atom_acqrel_add_u32(&st->done[b], 1u) == NSLICE - 1);
                bar_sync(3, NEPI * 32);
                if (sm.elast && et < DM / 4) {
                    const float4 a = ld_gpu_v4(reinterpret_cast<const float4*>(&st->acc[b][col]));
                    const __nv_bfloat162 r0 = __floats2bfloat162_rn(a.x, a.y), r1 = __floats2bfloat162_rn(a.z, a.w);
                    uint2 pk;
                    pk.x = *reinterpret_cast<const uint32_t*>(&r0);
                    pk.y = *reinterpret_cast<const uint32_t*>(&r1);
                    *reinterpret_cast<uint2*>(out + b * DM + col) = pk;
                }
            }
        } else {
            unsigned int* p = reinterpret_cast<unsigned int*>(&g_state[(epoch & 1) ^ 1]);
            for (int i = (cta - NSLICE) * (NEPI * 32) + et; i < (int)(sizeof(State) / 4); i += (NCTA - NSLICE) * NEPI * 32) p[i] = 0u;
        }
        return;
    }

    if (cta < NSLICE) {
        const int rg = tid >> 2;
        float a[32];
#pragma unroll
        for (int j = 0; j < 32; j++) a[j] = 0.f;
#pragma unroll
        for (int i = 0; i < 7; i++) {
#pragma unroll
            for (int b = 0; b < NB; b++) axpy8(a + 8 * b, sm.xs[b][rg * 7 + i], w[i]);
        }
        if (lane == 0) mbar_arrive(smem_u32(&sm.wq_bar));
        const bool h16 = lane & 16, h8 = lane & 8, h4 = lane & 4;
        float r1[16], r2[8], r3[4];
#pragma unroll
        for (int k = 0; k < 16; k++)
            r1[k] = (h16 ? a[k + 16] : a[k]) + __shfl_xor_sync(0xffffffffu, h16 ? a[k] : a[k + 16], 16);
#pragma unroll
        for (int k = 0; k < 8; k++)
            r2[k] = (h8 ? r1[k + 8] : r1[k]) + __shfl_xor_sync(0xffffffffu, h8 ? r1[k] : r1[k + 8], 8);
#pragma unroll
        for (int k = 0; k < 4; k++)
            r3[k] = (h4 ? r2[k + 4] : r2[k]) + __shfl_xor_sync(0xffffffffu, h4 ? r2[k] : r2[k + 4], 4);
        const int bb = lane >> 3;
        const int cc = (lane & 3) * 8 + (h4 ? 4 : 0);
        *reinterpret_cast<float4*>(&sm.qred[warp][bb * 32 + cc]) = make_float4(r3[0], r3[1], r3[2], r3[3]);
        bar_sync(1, NCW * 32);
        if (tid < 64) {
            float s0 = 0.f, s1 = 0.f;
#pragma unroll
            for (int g = 0; g < NCW; g++) {
                const float2 t = *reinterpret_cast<const float2*>(&sm.qred[g][tid * 2]);
                s0 += t.x; s1 += t.y;
            }
            const __nv_bfloat162 qv = __floats2bfloat162_rn(s0, s1);
            st_ll(&g_qll[((tid >> 4) * (NH * DH) + cta * 32) / 2 + (tid & 15)], *reinterpret_cast<const uint32_t*>(&qv), tag);
        }
    } else if (tid == 0) {
        mbar_arrive(smem_u32(&sm.wq_bar));
    }

    float q[8], o[8];
#pragma unroll
    for (int j = 0; j < 8; j++) { q[j] = 0.f; o[j] = 0.f; }
    float m = -INFINITY, l = 0.f;
    const bool hi16 = lane & 16, hi8 = lane & 8;
    const uint32_t tile_off = (uint32_t)(warp * KPW * DH * 2 + lane * 16);
    int s = 0, ph = 0, cur = -1, nt = 0, fl = 0;

    while (true) {
        mbar_wait(smem_u32(&sm.full[s]), ph);
        const int desc = sm.tile_pair[s];
        const int P = desc < 0 ? -1 : (desc & 0xffff);
        const bool half = desc & 0x10000;
        if (P != cur) {
            if (cur >= 0) {
                const int fb = fl & 1;
                *reinterpret_cast<float4*>(&sm.fo[fb][warp][lane * 8]) = make_float4(o[0], o[1], o[2], o[3]);
                *reinterpret_cast<float4*>(&sm.fo[fb][warp][lane * 8 + 4]) = make_float4(o[4], o[5], o[6], o[7]);
                if (lane == 0) { sm.fml[fb][warp][0] = m; sm.fml[fb][warp][1] = l; }
                bar_sync(1, NCW * 32);
                float M = sm.fml[fb][0][0];
#pragma unroll
                for (int g = 1; g < NCW; g++) M = fmaxf(M, sm.fml[fb][g][0]);
                float L = 0.f, O = 0.f;
#pragma unroll
                for (int g = 0; g < NCW; g++) {
                    const float wg = ex2(sm.fml[fb][g][0] - M);
                    L = fmaf(wg, sm.fml[fb][g][1], L);
                    O = fmaf(wg, sm.fo[fb][g][tid], O);
                }
                __stcg(&g_rec[cur][cta][tid], O);
                const int slot = fl % SIGQ;
                if (tid == 0) {
                    __stcg(&g_hdr[cur][cta], make_float4(M, L, __uint_as_float(tag), 0.f));
                    mbar_wait(smem_u32(&sm.sig_empty[slot]), ((fl / SIGQ) & 1) ^ 1);
                    sm.sig_pair[slot] = cur;
                    sm.sig_nt[slot] = nt;
                }
                __syncwarp();
                if (lane == 0) mbar_arrive(smem_u32(&sm.sig_full[slot]));
                fl++;
            }
            if (P < 0) break;
            cur = P; nt = 0; m = -INFINITY; l = 0.f;
            {
                uint32_t n = 0;
                while (ld_acquire_cta(&sm.qready[P]) == 0) {
                    if (++n > (1u << 26)) __trap();
                }
            }
            const uint4 qq = lds128(smem_u32(&sm.qall[P][lane * 8]));
            q[0] = bf_lo(qq.x) * SCALE_LOG2E; q[1] = bf_hi(qq.x) * SCALE_LOG2E;
            q[2] = bf_lo(qq.y) * SCALE_LOG2E; q[3] = bf_hi(qq.y) * SCALE_LOG2E;
            q[4] = bf_lo(qq.z) * SCALE_LOG2E; q[5] = bf_hi(qq.z) * SCALE_LOG2E;
            q[6] = bf_lo(qq.w) * SCALE_LOG2E; q[7] = bf_hi(qq.w) * SCALE_LOG2E;
#pragma unroll
            for (int j = 0; j < 8; j++) o[j] = 0.f;
        }
        if (half && warp >= NCW / 2) {
            __syncwarp();
            if (lane == 0) mbar_arrive(smem_u32(&sm.empty[s]));
        } else {
            const uint32_t ka = smem_u32(sm.stage[s][0]) + tile_off;
            uint4 kk[KPW], vv[KPW];
#pragma unroll
            for (int j = 0; j < KPW; j++) kk[j] = lds128(ka + j * (DH * 2));
#pragma unroll
            for (int j = 0; j < KPW; j++) vv[j] = lds128(ka + TILE + j * (DH * 2));
            float sc[KPW];
#pragma unroll
            for (int j = 0; j < KPW; j++) sc[j] = dot8(kk[j], q);
            float k0 = hi16 ? sc[2] : sc[0], k1 = hi16 ? sc[3] : sc[1];
            const float s0 = hi16 ? sc[0] : sc[2], s1 = hi16 ? sc[1] : sc[3];
            k0 += __shfl_xor_sync(0xffffffffu, s0, 16);
            k1 += __shfl_xor_sync(0xffffffffu, s1, 16);
            float kv = hi8 ? k1 : k0;
            const float sv = hi8 ? k0 : k1;
            kv += __shfl_xor_sync(0xffffffffu, sv, 8);
            kv += __shfl_xor_sync(0xffffffffu, kv, 4);
            kv += __shfl_xor_sync(0xffffffffu, kv, 2);
            kv += __shfl_xor_sync(0xffffffffu, kv, 1);
            __syncwarp();
            if (lane == 0) mbar_arrive(smem_u32(&sm.empty[s]));
            float mx = fmaxf(kv, __shfl_xor_sync(0xffffffffu, kv, 8));
            mx = fmaxf(mx, __shfl_xor_sync(0xffffffffu, mx, 16));
            const float mn = fmaxf(m, mx);
            const float p = ex2(kv - mn);
            const float alpha = ex2(m - mn);
            m = mn;
            const float p0 = __shfl_sync(0xffffffffu, p, 0);
            const float p1 = __shfl_sync(0xffffffffu, p, 8);
            const float p2 = __shfl_sync(0xffffffffu, p, 16);
            const float p3 = __shfl_sync(0xffffffffu, p, 24);
            l = fmaf(l, alpha, (p0 + p1) + (p2 + p3));
#pragma unroll
            for (int j = 0; j < 8; j++) o[j] *= alpha;
            axpy8(o, p0, vv[0]);
            axpy8(o, p1, vv[1]);
            axpy8(o, p2, vv[2]);
            axpy8(o, p3, vv[3]);
        }
        nt += half ? 1 : 2;
        if (++s == STAGES) { s = 0; ph ^= 1; }
    }
    {
        const int slot = fl % SIGQ;
        if (tid == 0) {
            mbar_wait(smem_u32(&sm.sig_empty[slot]), ((fl / SIGQ) & 1) ^ 1);
            sm.sig_pair[slot] = -1;
        }
        __syncwarp();
        if (lane == 0) mbar_arrive(smem_u32(&sm.sig_full[slot]));
    }
}

constexpr int FB_SPLIT = 32;
__device__ float g_fb_q[NPAIR * DH];

__global__ void __launch_bounds__(256) fb_q_kernel(const __nv_bfloat16* __restrict__ x, const __nv_bfloat16* __restrict__ wq) {
    const int pair = blockIdx.x, b = pair / NH, c = (pair % NH) * DH + threadIdx.x;
    float s = 0.f;
    for (int r = 0; r < DM; r++) s = fmaf(__bfloat162float(x[b * DM + r]), __bfloat162float(wq[(size_t)r * (NH * DH) + c]), s);
    g_fb_q[pair * DH + threadIdx.x] = round_bf16(s) * SCALE_LOG2E;
}

__global__ void __launch_bounds__(256) fb_attn_kernel(const __nv_bfloat16* __restrict__ kc, const __nv_bfloat16* __restrict__ vc) {
    __shared__ float so[NCW][DH];
    __shared__ float sml[NCW][2];
    const int pair = blockIdx.y, split = blockIdx.x, warp = threadIdx.x >> 5, lane = threadIdx.x & 31;
    float q[8], o[8];
#pragma unroll
    for (int j = 0; j < 8; j++) { q[j] = g_fb_q[pair * DH + lane * 8 + j]; o[j] = 0.f; }
    float m = -INFINITY, l = 0.f;
    constexpr int KPS = SK / FB_SPLIT;
    for (int k = warp; k < KPS; k += NCW) {
        const size_t row = ((size_t)pair * SK + split * KPS + k) * DH + lane * 8;
        float s = dot8(ldg_nc(kc + row), q);
#pragma unroll
        for (int t = 16; t; t >>= 1) s += __shfl_xor_sync(0xffffffffu, s, t);
        const float mn = fmaxf(m, s), p = ex2(s - mn), alpha = ex2(m - mn);
        m = mn;
        l = fmaf(l, alpha, p);
#pragma unroll
        for (int j = 0; j < 8; j++) o[j] *= alpha;
        axpy8(o, p, ldg_nc(vc + row));
    }
#pragma unroll
    for (int j = 0; j < 8; j++) so[warp][lane * 8 + j] = o[j];
    if (lane == 0) { sml[warp][0] = m; sml[warp][1] = l; }
    __syncthreads();
    float M = sml[0][0];
    for (int g = 1; g < NCW; g++) M = fmaxf(M, sml[g][0]);
    float L = 0.f, O = 0.f;
    for (int g = 0; g < NCW; g++) {
        const float wg = ex2(sml[g][0] - M);
        L = fmaf(wg, sml[g][1], L);
        O = fmaf(wg, so[g][threadIdx.x], O);
    }
    g_rec[pair][split][threadIdx.x] = O;
    if (threadIdx.x == 0) g_hdr[pair][split] = make_float4(M, L, 0.f, 0.f);
}

__global__ void __launch_bounds__(DM) fb_out_kernel(const __nv_bfloat16* __restrict__ wo, __nv_bfloat16* __restrict__ out) {
    __shared__ float so[NH * DH];
    const int b = blockIdx.x;
    for (int i = threadIdx.x; i < NH * DH; i += DM) {
        const int pair = b * NH + i / DH, d = i % DH;
        float M = -INFINITY;
        for (int r = 0; r < FB_SPLIT; r++) M = fmaxf(M, g_hdr[pair][r].x);
        float L = 0.f, O = 0.f;
        for (int r = 0; r < FB_SPLIT; r++) {
            const float wg = ex2(g_hdr[pair][r].x - M);
            L = fmaf(wg, g_hdr[pair][r].y, L);
            O = fmaf(wg, g_rec[pair][r][d], O);
        }
        so[i] = round_bf16(O / L);
    }
    __syncthreads();
    float y = 0.f;
    for (int r = 0; r < NH * DH; r++) y = fmaf(so[r], __bfloat162float(wo[(size_t)r * DM + threadIdx.x]), y);
    out[b * DM + threadIdx.x] = __float2bfloat16_rn(y);
}

}

extern "C" void kernel_launch(void* const* d_in, const int* in_sizes, int n_in,
                              void* d_out, int out_size) {
    const __nv_bfloat16* x = (const __nv_bfloat16*)d_in[0];
    const __nv_bfloat16* kc = (const __nv_bfloat16*)d_in[1];
    const __nv_bfloat16* vc = (const __nv_bfloat16*)d_in[2];
    const __nv_bfloat16* wq = (const __nv_bfloat16*)d_in[3];
    const __nv_bfloat16* wo = (const __nv_bfloat16*)d_in[4];
    __nv_bfloat16* out = (__nv_bfloat16*)d_out;

    int dev = 0, sms = 0, per_sm = 0;
    cudaGetDevice(&dev);
    cudaDeviceGetAttribute(&sms, cudaDevAttrMultiProcessorCount, dev);
    bool fused = cudaFuncSetAttribute(mha_decode_kernel, cudaFuncAttributeMaxDynamicSharedMemorySize,
                                      (int)sizeof(Smem)) == cudaSuccess;
    fused = fused && cudaOccupancyMaxActiveBlocksPerMultiprocessor(&per_sm, mha_decode_kernel, NTHREADS, sizeof(Smem)) == cudaSuccess;
    fused = fused && (long long)sms * per_sm >= NCTA;
    if (fused) {
        mha_decode_kernel<<<NCTA, NTHREADS, sizeof(Smem)>>>(x, kc, vc, wq, wo, out);
    } else {
        (void)cudaGetLastError();
        fb_q_kernel<<<NPAIR, 256>>>(x, wq);
        fb_attn_kernel<<<dim3(FB_SPLIT, NPAIR), 256>>>(kc, vc);
        fb_out_kernel<<<NB, DM>>>(wo, out);
    }
}
```
